```python
import torch

def _softmax(x, axis=-1):
    return torch.softmax(x, dim=axis)

def _gelu(x):
    return torch.nn.functional.gelu(x, approximate='tanh')

def _silu(x):
    return torch.nn.functional.silu(x)

def _sigmoid(x):
    return torch.sigmoid(x)

def _layernorm(x, axis=-1, eps=1e-05):
    m = x.mean(dim=axis, keepdim=True)
    v = x.var(dim=axis, keepdim=True, unbiased=False)
    return (x - m) / torch.sqrt(v + eps)

def _scatter_add(tgt, idx, src, axis=0):
    return tgt.clone().index_add_(axis, idx, src)

def _segment_sum(src, seg, n):
    out = torch.zeros((n,) + src.shape[1:], dtype=src.dtype)
    return out.index_add_(0, seg, src)

def _pad(x, pw):
    flat = tuple((v for pair in reversed(pw) for v in pair))
    return torch.nn.functional.pad(x, flat)
kernel_name = 'adaLN_cond__mha_block_cached__glu_gated_geglu__prompt'

def setup_inputs():

    _w = lambda a: (lambda t: t.to(torch.bfloat16) if t.is_floating_point() else t)(torch.as_tensor(a))

    def _A_setup():
        B, Sq, D = (1, 2048, 576)
        H, Sk, Dh = (32, 2048, 128)
        return {'x': _w((lambda *s: torch.randn(*s, dtype=torch.bfloat16) * 0.05)(B, Sq, D)), 'k_cache': _w((lambda *s: torch.randn(*s, dtype=torch.bfloat16) * 0.8)(B, H, Sk, Dh)), 'v_cache': _w((lambda *s: torch.randn(*s, dtype=torch.bfloat16) * 3.2)(B, H, Sk, Dh)), 'wq': _w((lambda *s: torch.randn(*s, dtype=torch.bfloat16) * 0.8)(D, H * Dh) * D ** (-0.5)), 'wo': _w((lambda *s: torch.randn(*s, dtype=torch.bfloat16) * 3.2)(H * Dh, D) * (H * Dh) ** (-0.5))}
    _A_in = _A_setup()

    def _B_setup():
        B, S, Dm, Df = (1, 2048, 576, 4608)
        return {'x': _w((lambda *s: torch.randn(*s, dtype=torch.bfloat16) * 0.05)(B, S, Dm)), 'w_gate': _w((lambda *s: torch.randn(*s, dtype=torch.bfloat16) * 3.2)(Dm, Df) * Dm ** (-0.5)), 'w_up': _w((lambda *s: torch.randn(*s, dtype=torch.bfloat16) * 3.2)(Dm, Df) * Dm ** (-0.5)), 'w_down': _w((lambda *s: torch.randn(*s, dtype=torch.bfloat16) * 3.2)(Df, Dm) * Df ** (-0.5))}
    _B_in = _B_setup()
    return {'A_x': _A_in['x'], 'A_k_cache': _A_in['k_cache'], 'A_v_cache': _A_in['v_cache'], 'A_wq': _A_in['wq'], 'A_wo': _A_in['wo'], 'B_x': _B_in['x'], 'B_w_gate': _B_in['w_gate'], 'B_w_up': _B_in['w_up'], 'B_w_down': _B_in['w_down'], 'c': _w((lambda *s: torch.randn(*s, dtype=torch.bfloat16) * 0.4)(1, 576) * 8.0), 'w_mod': _w((lambda *s: torch.randn(*s, dtype=torch.bfloat16) * 0.4)(576, 6 * 576) * 576 ** (-0.5) * 8.0)}

def reference(A_x, A_k_cache, A_v_cache, A_wq, A_wo, B_x, B_w_gate, B_w_up, B_w_down, c, w_mod):

    def _A_ref(x, k_cache, v_cache, wq, wo):
        B, Sq, D = x.shape
        H, Dh = (32, 128)
        q = (lambda x, *d: x.permute(*d))((x @ wq).reshape(B, Sq, H, Dh), 0, 2, 1, 3)
        scores = torch.einsum('bhqd,bhkd->bhqk', q, k_cache) * Dh ** (-0.5)
        p = _softmax(scores, axis=-1)
        o = torch.einsum('bhqk,bhkd->bhqd', p, v_cache)
        return (lambda x, *d: x.permute(*d))(o, 0, 2, 1, 3).reshape(B, Sq, H * Dh) @ wo

    def _B_ref(x, w_gate, w_up, w_down):
        g = torch.einsum('bsd,df->bsf', x, w_gate)
        u = torch.einsum('bsd,df->bsf', x, w_up)
        h = _gelu(g) * u
        return torch.einsum('bsf,fd->bsd', h, w_down)
    x = A_x
    mod = (_silu(c) @ w_mod).reshape(c.shape[0], 6, 1, -1)
    sa, ca, ga, sb, cb, gb = (mod[:, 0].clone(), mod[:, 1].clone(), mod[:, 2].clone(), mod[:, 3].clone(), mod[:, 4].clone(), mod[:, 5].clone())
    h = _layernorm(x, axis=-1) * (1 + ca) + sa
    x = x + ga * _A_ref(h, A_k_cache, A_v_cache, A_wq, A_wo)
    h = _layernorm(x, axis=-1) * (1 + cb) + sb
    x = x + gb * _B_ref(h, B_w_gate, B_w_up, B_w_down)
    return x
```

```cpp
#include <cuda_runtime.h>
#include <cuda_bf16.h>
#include <cuda.h>
#include <stdint.h>

namespace {

constexpr int SEQ = 2048;
constexpr int DM = 576;
constexpr int DH = 128;
constexpr int DF = 4608;
constexpr int NCTA = 128;
constexpr int NMOD1 = 72;
constexpr int NMOD2 = 288;

constexpr uint32_t SLOT_BYTES = 16384;
constexpr uint32_t S_OFF = 8 * SLOT_BYTES;
constexpr uint32_t WM_OFF = 3 * SLOT_BYTES;
constexpr uint32_t X_OFF = 5 * SLOT_BYTES;
constexpr uint32_t MISC_OFF = 14 * SLOT_BYTES;
constexpr uint32_t BAR_OFF = MISC_OFF;
constexpr uint32_t XBAR_OFF = MISC_OFF + 128;
constexpr uint32_t TAB_OFF = MISC_OFF + 192;
constexpr uint32_t TAB_STRIDE = 592;
constexpr uint32_t PART_OFF = TAB_OFF + 4 * TAB_STRIDE;
constexpr uint32_t SMEM_BYTES = PART_OFF + 512;

constexpr uint32_t SPIN_LIMIT = 1u << 24;
#define X_DELAY 1200u

constexpr int C_MOD2 = 32, C_ZERO = 64, C_B2 = C_ZERO + 128 * 8, C_B4 = C_B2 + 128 * 8,
              C_TOTAL = C_B4 + 128 * 8;

__device__ __align__(16) uint32_t g_tab1[288 * 4];
__device__ __align__(16) uint16_t g_tab2[288 * 8];
constexpr int ACC_N = 32 * 32, PART_N = 8 * 4 * 32, H2_N = 36 * 32;
__device__ uint4 g_acc[2 * 128 * ACC_N];
__device__ uint4 g_part[2 * 128 * PART_N];
__device__ uint4 g_h2[128 * H2_N];
constexpr uint32_t EMPTY = 0xffffffffu;
__device__ unsigned int g_cnt[C_TOTAL];
#define PSTAMP(i) do { } while (0)
#define TSTAMP(i) do { } while (0)

__device__ __forceinline__ uint32_t smem_u32(const void* p) { return (uint32_t)__cvta_generic_to_shared(p); }

__device__ __forceinline__ int tid_now() {
    int t;
    asm volatile("mov.u32 %0, %%tid.x;" : "=r"(t));
    return t;
}
__device__ __forceinline__ void die() { asm volatile("st.global.u32 [%0], %1;" ::"l"(0ull), "r"(0u) : "memory"); }

__device__ __forceinline__ void mbar_init(uint32_t bar, uint32_t cnt) {
    asm volatile("mbarrier.init.shared::cta.b64 [%0], %1;" ::"r"(bar), "r"(cnt) : "memory");
}
__device__ __forceinline__ void mbar_expect_tx(uint32_t bar, uint32_t bytes) {
    asm volatile("mbarrier.arrive.expect_tx.shared::cta.b64 _, [%0], %1;" ::"r"(bar), "r"(bytes) : "memory");
}
__device__ __forceinline__ bool mbar_try(uint32_t bar, uint32_t parity) {
    uint32_t ok;
    asm volatile("{\n.reg .pred p;\nmbarrier.try_wait.parity.shared::cta.b64 p, [%1], %2;\nselp.u32 %0, 1, 0, p;\n}\n"
                 : "=r"(ok) : "r"(bar), "r"(parity) : "memory");
    return ok != 0;
}
__device__ __forceinline__ void mbar_wait(uint32_t bar, uint32_t parity) {
    asm volatile(
        "{\n.reg .pred p;\n.reg .u32 n;\n.reg .u64 z;\n"
        "mov.u32 n, 0;\n"
        "WAIT_LOOP:\n"
        "mbarrier.try_wait.parity.shared::cta.b64 p, [%0], %1;\n"
        "@p bra WAIT_DONE;\n"
        "add.u32 n, n, 1;\n"
        "setp.lt.u32 p, n, %2;\n"
        "@p bra WAIT_LOOP;\n"
        "mov.u64 z, 0;\n"
        "st.global.u32 [z], n;\n"
        "WAIT_DONE:\n}\n" ::"r"(bar), "r"(parity), "n"(SPIN_LIMIT)
        : "memory");
}
__device__ __forceinline__ void mbar_arrive_cluster(uint32_t cluster_addr) {
    asm volatile("mbarrier.arrive.shared::cluster.b64 _, [%0];" ::"r"(cluster_addr) : "memory");
}
__device__ __forceinline__ uint32_t mapa(uint32_t addr, uint32_t cta) {
    uint32_t r;
    asm volatile("mapa.shared::cluster.u32 %0, %1, %2;" : "=r"(r) : "r"(addr), "r"(cta));
    return r;
}
__device__ __forceinline__ void cluster_arrive() { asm volatile("barrier.cluster.arrive.relaxed.aligned;" ::: "memory"); }
__device__ __forceinline__ void cluster_wait() { asm volatile("barrier.cluster.wait.acquire.aligned;" ::: "memory"); }
template <int ID, int N> __device__ __forceinline__ void bar_arrive() { asm volatile("bar.arrive %0, %1;" ::"n"(ID), "n"(N) : "memory"); }
template <int ID, int N> __device__ __forceinline__ void bar_sync() { asm volatile("bar.sync %0, %1;" ::"n"(ID), "n"(N) : "memory"); }
__device__ __forceinline__ void bar_sync_r(int id, int n) { asm volatile("bar.sync %0, %1;" ::"r"(id), "r"(n) : "memory"); }
__device__ __forceinline__ void bar_arrive_r(int id, int n) { asm volatile("bar.arrive %0, %1;" ::"r"(id), "r"(n) : "memory"); }

__device__ __forceinline__ void warp_expect_tx(uint32_t bar, uint32_t bytes) {
    asm volatile("{\n.reg .pred p;\nelect.sync _|p, 0xffffffff;\n@p mbarrier.arrive.expect_tx.shared::cta.b64 _, [%0], %1;\n}\n" ::"r"(bar),
                 "r"(bytes)
                 : "memory");
}
__device__ __forceinline__ void warp_tma_mc(uint32_t dst, const CUtensorMap* tm, uint32_t bar, int col, int row) {
    asm volatile(
        "{\n.reg .pred p;\nelect.sync _|p, 0xffffffff;\n"
        "@p cp.async.bulk.tensor.2d.shared::cluster.global.mbarrier::complete_tx::bytes.multicast::cluster "
        "[%0], [%1, {%3, %4}], [%2], %5;\n}\n" ::"r"(dst), "l"(tm), "r"(bar), "r"(col), "r"(row), "h"((uint16_t)3)
        : "memory");
}
__device__ __forceinline__ void warp_prefetch_l2(const CUtensorMap* tm, int col, int row) {
    asm volatile("{\n.reg .pred p;\nelect.sync _|p, 0xffffffff;\n@p cp.async.bulk.prefetch.tensor.2d.L2.global.tile [%0, {%1, %2}];\n}\n" ::"l"(tm),
                 "r"(col), "r"(row)
                 : "memory");
}

__device__ __forceinline__ void tma_local(uint32_t dst, const CUtensorMap* tm, uint32_t bar, int col, int row) {
    asm volatile("cp.async.bulk.tensor.2d.shared::cluster.global.mbarrier::complete_tx::bytes [%0], [%1, {%3, %4}], [%2];" ::"r"(dst),
                 "l"(tm), "r"(bar), "r"(col), "r"(row)
                 : "memory");
}
__device__ __forceinline__ void prefetch_map(const CUtensorMap* tm) { asm volatile("prefetch.tensormap [%0];" ::"l"(tm) : "memory"); }
__device__ __forceinline__ void ldsm4(uint32_t addr, uint32_t& a, uint32_t& b, uint32_t& c, uint32_t& d) {
    asm volatile("ldmatrix.sync.aligned.m8n8.x4.shared.b16 {%0,%1,%2,%3}, [%4];" : "=r"(a), "=r"(b), "=r"(c), "=r"(d) : "r"(addr) : "memory");
}

__device__ __forceinline__ uint32_t ld_acquire(const unsigned int* p) {
    uint32_t v;
    asm volatile("ld.acquire.gpu.global.u32 %0, [%1];" : "=r"(v) : "l"(p) : "memory");
    return v;
}
__device__ __forceinline__ void warp_wait_count(const unsigned int* p, uint32_t target) {
    uint32_t n = 0;
#pragma unroll 1
    while (!__all_sync(0xffffffffu, (int)(ld_acquire(p) - target) >= 0)) {
        if (++n > SPIN_LIMIT) die();
    }
}
__device__ __forceinline__ void warp_signal_count(unsigned int* p) {
    asm volatile(
        "{\n.reg .pred p;\nfence.acq_rel.gpu;\nelect.sync _|p, 0xffffffff;\n@p red.relaxed.gpu.global.add.u32 [%0], 1;\n}\n" ::"l"(p)
        : "memory");
}

__device__ __forceinline__ void wg_fence() { asm volatile("wgmma.fence.sync.aligned;" ::: "memory"); }
__device__ __forceinline__ void wg_commit() { asm volatile("wgmma.commit_group.sync.aligned;" ::: "memory"); }
template <int N> __device__ __forceinline__ void wg_wait() { asm volatile("wgmma.wait_group.sync.aligned %0;" ::"n"(N) : "memory"); }

template <int N> __device__ __forceinline__ void fence_regs(float (&d)[N]) {
#pragma unroll
    for (int i = 0; i < N; i++) asm volatile("" : "+f"(d[i])::"memory");
}
template <int N> __device__ __forceinline__ void kill_regs(float (&d)[N]) {
#pragma unroll
    for (int i = 0; i < N; i++) d[i] = 0.f;
}
template <int N> __device__ __forceinline__ void fence_regs(uint32_t (&d)[N]) {
#pragma unroll
    for (int i = 0; i < N; i++) asm volatile("" : "+r"(d[i])::"memory");
}

constexpr uint32_t DESC_HI = 64u | (1u << 30);
constexpr uint32_t DESC_LBO_N = 512u << 16;
constexpr uint32_t DESC_LBO_K = 1u << 16;

#define F8(c, d, o) c(d[o + 0]), c(d[o + 1]), c(d[o + 2]), c(d[o + 3]), c(d[o + 4]), c(d[o + 5]), c(d[o + 6]), c(d[o + 7])
#define REGS64                                                            \
    "{%0,%1,%2,%3,%4,%5,%6,%7,%8,%9,%10,%11,%12,%13,%14,%15,"             \
    "%16,%17,%18,%19,%20,%21,%22,%23,%24,%25,%26,%27,%28,%29,%30,%31,"    \
    "%32,%33,%34,%35,%36,%37,%38,%39,%40,%41,%42,%43,%44,%45,%46,%47,"    \
    "%48,%49,%50,%51,%52,%53,%54,%55,%56,%57,%58,%59,%60,%61,%62,%63},"
#define REGS32                                                            \
    "{%0,%1,%2,%3,%4,%5,%6,%7,%8,%9,%10,%11,%12,%13,%14,%15,"             \
    "%16,%17,%18,%19,%20,%21,%22,%23,%24,%25,%26,%27,%28,%29,%30,%31},"

template <int TB, bool ACC>
__device__ __forceinline__ void mma128(float (&d)[64], uint32_t a0, uint32_t a1, uint32_t a2, uint32_t a3, uint32_t desc_lo) {
    if (ACC) {
        asm volatile(
            "{\n.reg .b64 db;\nmov.b64 db, {%68, %69};\n"
            "wgmma.mma_async.sync.aligned.m64n128k16.f32.bf16.bf16 " REGS64 "{%64,%65,%66,%67}, db, 1, 1, 1, %70;\n}\n"
            : F8("+f", d, 0), F8("+f", d, 8), F8("+f", d, 16), F8("+f", d, 24), F8("+f", d, 32), F8("+f", d, 40), F8("+f", d, 48),
              F8("+f", d, 56)
            : "r"(a0), "r"(a1), "r"(a2), "r"(a3), "r"(desc_lo), "r"(DESC_HI), "n"(TB));
    } else {
        asm volatile(
            "{\n.reg .b64 db;\nmov.b64 db, {%68, %69};\n"
            "wgmma.mma_async.sync.aligned.m64n128k16.f32.bf16.bf16 " REGS64 "{%64,%65,%66,%67}, db, 0, 1, 1, %70;\n}\n"
            : F8("=f", d, 0), F8("=f", d, 8), F8("=f", d, 16), F8("=f", d, 24), F8("=f", d, 32), F8("=f", d, 40), F8("=f", d, 48),
              F8("=f", d, 56)
            : "r"(a0), "r"(a1), "r"(a2), "r"(a3), "r"(desc_lo), "r"(DESC_HI), "n"(TB));
    }
}
__device__ __forceinline__ void mma128_p(float (&d)[64], uint32_t a0, uint32_t a1, uint32_t a2, uint32_t a3, uint32_t desc_lo, uint32_t accum) {
    asm volatile(
        "{\n.reg .b64 db;\n.reg .pred p;\nsetp.ne.u32 p, %70, 0;\nmov.b64 db, {%68, %69};\n"
        "wgmma.mma_async.sync.aligned.m64n128k16.f32.bf16.bf16 " REGS64 "{%64,%65,%66,%67}, db, p, 1, 1, 1;\n}\n"
        : F8("+f", d, 0), F8("+f", d, 8), F8("+f", d, 16), F8("+f", d, 24), F8("+f", d, 32), F8("+f", d, 40), F8("+f", d, 48), F8("+f", d, 56)
        : "r"(a0), "r"(a1), "r"(a2), "r"(a3), "r"(desc_lo), "r"(DESC_HI), "r"(accum));
}
template <bool ACC>
__device__ __forceinline__ void mma64(float (&d)[32], uint32_t a0, uint32_t a1, uint32_t a2, uint32_t a3, uint32_t desc_lo) {
    if (ACC) {
        asm volatile(
            "{\n.reg .b64 db;\nmov.b64 db, {%36, %37};\n"
            "wgmma.mma_async.sync.aligned.m64n64k16.f32.bf16.bf16 " REGS32 "{%32,%33,%34,%35}, db, 1, 1, 1, 1;\n}\n"
            : F8("+f", d, 0), F8("+f", d, 8), F8("+f", d, 16), F8("+f", d, 24)
            : "r"(a0), "r"(a1), "r"(a2), "r"(a3), "r"(desc_lo), "r"(DESC_HI));
    } else {
        asm volatile(
            "{\n.reg .b64 db;\nmov.b64 db, {%36, %37};\n"
            "wgmma.mma_async.sync.aligned.m64n64k16.f32.bf16.bf16 " REGS32 "{%32,%33,%34,%35}, db, 0, 1, 1, 1;\n}\n"
            : F8("=f", d, 0), F8("=f", d, 8), F8("=f", d, 16), F8("=f", d, 24)
            : "r"(a0), "r"(a1), "r"(a2), "r"(a3), "r"(desc_lo), "r"(DESC_HI));
    }
}

__device__ __forceinline__ void mma_sync(float (&d)[4], uint32_t a0, uint32_t a1, uint32_t a2, uint32_t a3, uint32_t b0, uint32_t b1) {
    asm volatile("mma.sync.aligned.m16n8k16.row.col.f32.bf16.bf16.f32 {%0,%1,%2,%3}, {%4,%5,%6,%7}, {%8,%9}, {%0,%1,%2,%3};"
                 : "+f"(d[0]), "+f"(d[1]), "+f"(d[2]), "+f"(d[3])
                 : "r"(a0), "r"(a1), "r"(a2), "r"(a3), "r"(b0), "r"(b1));
}

__device__ __forceinline__ uint32_t pack_bf16(float lo, float hi) {
    uint32_t r;
    asm("cvt.rn.bf16x2.f32 %0, %1, %2;" : "=r"(r) : "f"(hi), "f"(lo));
    return r;
}
__device__ __forceinline__ float bf_lo(uint32_t v) { return __uint_as_float(v << 16); }
__device__ __forceinline__ float bf_hi(uint32_t v) { return __uint_as_float(v & 0xffff0000u); }
__device__ __forceinline__ float round_bf16(float v) { return __bfloat162float(__float2bfloat16_rn(v)); }
__device__ __forceinline__ uint32_t hfma2_bf16(uint32_t a, uint32_t b, uint32_t c) {
    uint32_t r;
    asm("fma.rn.bf16x2 %0, %1, %2, %3;" : "=r"(r) : "r"(a), "r"(b), "r"(c));
    return r;
}
__device__ __forceinline__ float ex2(float v) {
    float r;
    asm("ex2.approx.ftz.f32 %0, %1;" : "=f"(r) : "f"(v));
    return r;
}
__device__ __forceinline__ float rcp_fast(float v) {
    float r;
    asm("rcp.approx.ftz.f32 %0, %1;" : "=f"(r) : "f"(v));
    return r;
}
__device__ __forceinline__ float tanh_fast(float v) {
    float r;
    asm("tanh.approx.f32 %0, %1;" : "=f"(r) : "f"(v));
    return r;
}
__device__ __forceinline__ void sts128(uint32_t addr, uint32_t a, uint32_t b, uint32_t c, uint32_t d) {
    asm volatile("st.shared.v4.b32 [%0], {%1,%2,%3,%4};" ::"r"(addr), "r"(a), "r"(b), "r"(c), "r"(d) : "memory");
}
__device__ __forceinline__ void sts128_if(uint32_t on, uint32_t addr, uint32_t a, uint32_t b, uint32_t c, uint32_t d) {
    asm volatile("{\n.reg .pred p;\nsetp.ne.u32 p, %5, 0;\n@p st.shared.v4.b32 [%0], {%1,%2,%3,%4};\n}\n" ::"r"(addr), "r"(a), "r"(b), "r"(c),
                 "r"(d), "r"(on)
                 : "memory");
}
__device__ __forceinline__ void lds128(uint32_t addr, uint32_t& a, uint32_t& b, uint32_t& c, uint32_t& d) {
    asm volatile("ld.shared.v4.b32 {%0,%1,%2,%3}, [%4];" : "=r"(a), "=r"(b), "=r"(c), "=r"(d) : "r"(addr) : "memory");
}
__device__ __forceinline__ void red_bf16x8(uint4* p, const float* v) {
    asm volatile("red.global.add.noftz.v4.bf16x2 [%0], {%1,%2,%3,%4};" ::"l"(p), "r"(pack_bf16(v[0], v[1])), "r"(pack_bf16(v[2], v[3])),
                 "r"(pack_bf16(v[4], v[5])), "r"(pack_bf16(v[6], v[7]))
                 : "memory");
}
__device__ __forceinline__ uint4 ld_b128(const uint4* p) {
    uint4 v;
    asm volatile("{\n.reg .b128 q;\n.reg .b64 l, h;\nld.relaxed.gpu.global.b128 q, [%4];\nmov.b128 {l, h}, q;\n"
                 "mov.b64 {%0, %1}, l;\nmov.b64 {%2, %3}, h;\n}\n"
                 : "=r"(v.x), "=r"(v.y), "=r"(v.z), "=r"(v.w) : "l"(p) : "memory");
    return v;
}
__device__ __forceinline__ void st_b128(uint4* p, uint32_t a, uint32_t b, uint32_t c, uint32_t d) {
    asm volatile("{\n.reg .b128 q;\n.reg .b64 l, h;\nmov.b64 l, {%1, %2};\nmov.b64 h, {%3, %4};\nmov.b128 q, {l, h};\n"
                 "st.relaxed.gpu.global.b128 [%0], q;\n}\n" ::"l"(p), "r"(a), "r"(b), "r"(c), "r"(d) : "memory");
}
__device__ __forceinline__ void mma_k8(float (&d)[4], uint32_t a0, uint32_t a1, uint32_t b0) {
    asm volatile("mma.sync.aligned.m16n8k8.row.col.f32.bf16.bf16.f32 {%0,%1,%2,%3}, {%4,%5}, {%6}, {%0,%1,%2,%3};"
                 : "+f"(d[0]), "+f"(d[1]), "+f"(d[2]), "+f"(d[3])
                 : "r"(a0), "r"(a1), "r"(b0));
}

struct Ring {
    uint32_t slot;
    uint32_t bits;
    uint32_t ns;
    uint32_t full0;
    uint32_t rel0;
    uint32_t desc0;
    bool signaller;
    __device__ __forceinline__ void resize(uint32_t n) {
        ns = n;
        if (slot >= n) slot = 0;
    }
    __device__ __forceinline__ void advance() {
        bits ^= 1u << slot;
        if (++slot == ns) slot = 0;
    }
    __device__ __forceinline__ void wait_full() { mbar_wait(full0 + slot * 8, (bits >> slot) & 1); }
    __device__ __forceinline__ void release(uint32_t s) {
        if (signaller) mbar_arrive_cluster(rel0 + s * 8);
    }
    __device__ __forceinline__ void release_nobranch(uint32_t s) {
        asm volatile("{\n.reg .pred p;\nsetp.ne.u32 p, %1, 0;\n@p mbarrier.arrive.shared::cluster.b64 _, [%0];\n}\n" ::"r"(rel0 + s * 8),
                     "r"((uint32_t)signaller)
                     : "memory");
    }
    __device__ __forceinline__ uint32_t desc() { return desc0 + slot * (SLOT_BYTES >> 4); }
    __device__ __forceinline__ uint32_t desc_of(uint32_t s) { return desc0 + s * (SLOT_BYTES >> 4); }
    __device__ __forceinline__ bool try_pair() { return mbar_try(full0 + slot * 8 + 8, (bits >> (slot + 1)) & 1); }
    __device__ __forceinline__ uint32_t finish_pair(bool ok) {
        const uint32_t s = slot;
        if (!ok) mbar_wait(full0 + s * 8 + 8, (bits >> (s + 1)) & 1);
        bits ^= 2u << s;
        slot = (s + 2) & 7;
        return s;
    }
    __device__ __forceinline__ uint32_t wait_pair() { return finish_pair(false); }
    __device__ __forceinline__ void release_pair(uint32_t s) { release(s + 1); }
};
__device__ __forceinline__ uint32_t hh_off(int t) { return t < 6 ? S_OFF + t * SLOT_BYTES : (13 - t) * SLOT_BYTES; }
__device__ __forceinline__ uint32_t gu_slots(int t) { return t < 6 ? 8 : t == 6 ? 7 : 6; }

__device__ __forceinline__ float silu_bf16(__nv_bfloat16 c) {
    const float v = __bfloat162float(c);
    return round_bf16(__fdividef(v, 1.f + __expf(-v)));
}
__device__ __forceinline__ void fma8(float (&acc)[8], float sv, const uint4& w) {
    acc[0] = fmaf(sv, bf_lo(w.x), acc[0]);
    acc[1] = fmaf(sv, bf_hi(w.x), acc[1]);
    acc[2] = fmaf(sv, bf_lo(w.y), acc[2]);
    acc[3] = fmaf(sv, bf_hi(w.y), acc[3]);
    acc[4] = fmaf(sv, bf_lo(w.z), acc[4]);
    acc[5] = fmaf(sv, bf_hi(w.z), acc[5]);
    acc[6] = fmaf(sv, bf_lo(w.w), acc[6]);
    acc[7] = fmaf(sv, bf_hi(w.w), acc[7]);
}
template <bool ALL>
__device__ __forceinline__ float warp_reduce8(const float (&acc)[8], int lane) {
    const bool h4 = lane & 16, h2 = lane & 8, h1 = lane & 4;
    float r4[4], r2[2];
#pragma unroll
    for (int e = 0; e < 4; e++) r4[e] = (h4 ? acc[4 + e] : acc[e]) + __shfl_xor_sync(0xffffffffu, h4 ? acc[e] : acc[4 + e], 16);
#pragma unroll
    for (int e = 0; e < 2; e++) r2[e] = (h2 ? r4[2 + e] : r4[e]) + __shfl_xor_sync(0xffffffffu, h2 ? r4[e] : r4[2 + e], 8);
    float r = (h1 ? r2[1] : r2[0]) + __shfl_xor_sync(0xffffffffu, h1 ? r2[0] : r2[1], 4);
    r += __shfl_xor_sync(0xffffffffu, r, 2);
    if (ALL) r += __shfl_xor_sync(0xffffffffu, r, 1);
    return r;
}

template <class Prep>
__device__ __forceinline__ void gemm_tile128(float (&acc)[64], uint32_t (&a)[144], Ring& rg, int wg, bool full, Prep prep) {
    uint32_t prev = 0;
    prep(0);
    if (wg == 1) bar_sync<5, 256>();
#pragma unroll
    for (int kb = 0; kb < 9; kb++) {
        if (kb < 8 || full) {
            rg.wait_full();
            const uint32_t d = rg.desc() | DESC_LBO_N;
            wg_fence();
#pragma unroll
            for (int s = 0; s < 4; s++) {
                const int i = (kb * 4 + s) * 4;
                if ((kb | s) == 0) mma128<1, false>(acc, a[i], a[i + 1], a[i + 2], a[i + 3], d + s * 128);
                else mma128<1, true>(acc, a[i], a[i + 1], a[i + 2], a[i + 3], d + s * 128);
            }
            wg_commit();
            if (kb == 2 && wg == 0) bar_arrive<5, 256>();
            if (kb < 8) prep(kb + 1);
            if (kb > 0) { wg_wait<1>(); rg.release(prev); }
            prev = rg.slot;
            rg.advance();
        }
    }
    wg_wait<0>();
    rg.release(prev);
    fence_regs(acc);
}
__device__ __forceinline__ void gemm_tile64(float (&acc)[32], const uint32_t (&a)[144], Ring& rg, bool full) {
    uint32_t prev = 0;
#pragma unroll
    for (int kb = 0; kb < 5; kb++) {
        if (kb < 4 || full) {
            rg.wait_full();
            const uint32_t d = rg.desc() | DESC_LBO_N;
            wg_fence();
#pragma unroll
            for (int s = 0; s < (kb < 4 ? 8 : 4); s++) {
                const int i = (kb * 8 + s) * 4;
                if ((kb | s) == 0) mma64<false>(acc, a[i], a[i + 1], a[i + 2], a[i + 3], d + s * 128);
                else mma64<true>(acc, a[i], a[i + 1], a[i + 2], a[i + 3], d + s * 128);
            }
            wg_commit();
            if (kb > 0) { wg_wait<1>(); rg.release(prev); }
            prev = rg.slot;
            rg.advance();
        }
    }
    wg_wait<0>();
    rg.release(prev);
    fence_regs(acc);
}

__device__ __forceinline__ void issue_qk(float (&s)[64], const uint32_t (&q)[32], uint32_t desc) {
    const uint32_t d = desc | DESC_LBO_K;
#pragma unroll
    for (int k = 0; k < 8; k++) {
        const uint32_t dk = d + (k >> 2) * (SLOT_BYTES >> 4) + (k & 3) * 2;
        if (k == 0) mma128<0, false>(s, q[0], q[1], q[2], q[3], dk);
        else mma128<0, true>(s, q[4 * k], q[4 * k + 1], q[4 * k + 2], q[4 * k + 3], dk);
    }
    wg_commit();
}
__device__ __forceinline__ void issue_pv(float (&o)[64], const uint32_t (&p)[32], uint32_t desc, uint32_t accum = 1) {
    const uint32_t d = desc | DESC_LBO_N;
    mma128_p(o, p[0], p[1], p[2], p[3], d, accum);
#pragma unroll
    for (int k = 1; k < 8; k++)
        mma128<1, true>(o, p[4 * k], p[4 * k + 1], p[4 * k + 2], p[4 * k + 3], d + (k >> 2) * (SLOT_BYTES >> 4) + (k & 3) * 128);
    wg_commit();
}

constexpr float SCALE_LOG2 = 0.08838834764831845f * 1.4426950408889634f;

__device__ __forceinline__ void row_max(const float (&s)[64], float& x0, float& x1) {
    float a0 = fmaxf(s[0], s[1]), a1 = fmaxf(s[2], s[3]), b0 = fmaxf(s[4], s[5]), b1 = fmaxf(s[6], s[7]);
#pragma unroll
    for (int j = 2; j < 16; j += 2) {
        a0 = fmaxf(a0, fmaxf(s[4 * j], s[4 * j + 1]));
        a1 = fmaxf(a1, fmaxf(s[4 * j + 2], s[4 * j + 3]));
        b0 = fmaxf(b0, fmaxf(s[4 * j + 4], s[4 * j + 5]));
        b1 = fmaxf(b1, fmaxf(s[4 * j + 6], s[4 * j + 7]));
    }
    x0 = fmaxf(a0, b0);
    x1 = fmaxf(a1, b1);
    x0 = fmaxf(x0, __shfl_xor_sync(0xffffffffu, x0, 1));
    x1 = fmaxf(x1, __shfl_xor_sync(0xffffffffu, x1, 1));
    x0 = fmaxf(x0, __shfl_xor_sync(0xffffffffu, x0, 2));
    x1 = fmaxf(x1, __shfl_xor_sync(0xffffffffu, x1, 2));
}
template <int J0, int J1, int NP>
__device__ __forceinline__ void exp_pack(uint32_t (&p)[NP], const float (&s)[64], float n0, float n1, float& t0, float& t1) {
#pragma unroll
    for (int j = J0; j < J1; j++) {
        const float e0 = ex2(fmaf(s[4 * j], SCALE_LOG2, n0));
        const float e1 = ex2(fmaf(s[4 * j + 1], SCALE_LOG2, n0));
        const float e2 = ex2(fmaf(s[4 * j + 2], SCALE_LOG2, n1));
        const float e3 = ex2(fmaf(s[4 * j + 3], SCALE_LOG2, n1));
        t0 += e0 + e1;
        t1 += e2 + e3;
        p[2 * j] = pack_bf16(e0, e1);
        p[2 * j + 1] = pack_bf16(e2, e3);
    }
}
constexpr int JSPLIT0 = 3;
constexpr int JSPLIT = 9;
constexpr float P_BOUND = 1099511627776.f;
__device__ __forceinline__ void pack_frag(uint32_t (&p)[32], const float (&s)[64]) {
#pragma unroll
    for (int i = 0; i < 32; i++) p[i] = pack_bf16(s[2 * i], s[2 * i + 1]);
}

struct Maps {
    CUtensorMap x, wq, k, v, wo, wg, wu, wd, wm;
};

__global__ void __cluster_dims__(2, 1, 1) __launch_bounds__(384, 1)
mega_kernel(const __grid_constant__ Maps maps, const __nv_bfloat16* __restrict__ x, const __nv_bfloat16* __restrict__ cvec,
            const __nv_bfloat16* __restrict__ w_mod, __nv_bfloat16* out) {
    extern __shared__ __align__(1024) uint8_t smem[];
    const uint32_t sb = smem_u32(smem);
    const int tid = threadIdx.x;
    const int b = blockIdx.x;
    const int rank = b & 1;
    const int cl = b >> 1;
    const int hg = cl >> 3;
    const int qt = (cl & 7) * 2 + rank;
    const int wg = __shfl_sync(0xffffffffu, tid >> 7, 0);

    if (wg == 2) {
        const uint32_t t_entry = (uint32_t)clock64();
        asm volatile("setmaxnreg.dec.sync.aligned.u32 24;");
        if (tid == 256) {
            if (sb & 1023) die();
            prefetch_map(&maps.wm);
            prefetch_map(&maps.x);
            mbar_init(sb + XBAR_OFF + 32, 1);
            mbar_init(sb + XBAR_OFF + 40, 1);
            mbar_init(sb + XBAR_OFF + 48, 1);
            for (int i = 0; i < 3; i++) mbar_init(sb + XBAR_OFF + i * 8, 1);
            mbar_init(sb + XBAR_OFF + 24, 3);
            for (int i = 0; i < 8; i++) {
                mbar_init(sb + BAR_OFF + i * 8, 1);
                mbar_init(sb + BAR_OFF + 64 + i * 8, 4);
            }
            asm volatile("fence.mbarrier_init.release.cluster;" ::: "memory");
        }
        __syncwarp();
        cluster_arrive();
        if (tid == 256) {
            if (b < NMOD1) {
                mbar_expect_tx(sb + XBAR_OFF + 32, DM * 32);
                for (int i = 0; i < 3; i++) tma_local(sb + WM_OFF + i * 6144, &maps.wm, sb + XBAR_OFF + 32, b * 16, i * 192);
            }
            PSTAMP(7);
            for (int i = 0; i < 3; i++) mbar_expect_tx(sb + XBAR_OFF + i * 8, 3 * SLOT_BYTES);
            while ((uint32_t)clock64() - t_entry < X_DELAY) {}
#pragma unroll 1
            for (int i = 0; i < 18; i++)
                tma_local(sb + X_OFF + i * 8192, &maps.x, sb + XBAR_OFF + (i / 6) * 8, (i >> 1) * 64, qt * 128 + (i & 1) * 64);
#pragma unroll 1
            for (int i = 1; i < 8; i++) prefetch_map(&maps.x + i);
        }
        __syncwarp();
        cluster_wait();
        if (__shfl_sync(0xffffffffu, tid >> 5, 0) == 8) {
            uint32_t slot = 0;
            uint32_t bits = 0x07u;
            const uint32_t full0 = sb + BAR_OFF, empty0 = sb + BAR_OFF + 64;
            const uint32_t dst0 = sb + rank * 8192;
            mbar_wait(sb + XBAR_OFF + 8, 0);
#pragma unroll 1
            for (int i = qt; i < 72; i += 16) warp_prefetch_l2(&maps.wq, hg * 512 + 448 - (i / 9) * 64, (i % 9) * 64);
#pragma unroll 1
            for (int i = qt; i < 32; i += 16)
                warp_prefetch_l2((i & 4) ? &maps.v : &maps.k, (i & 1) * 64, hg * 4 * SEQ + (i >> 3) * 128 + (i & 2) * 32);
#pragma unroll 1
            for (int seg = 0; seg < 6; seg++) {
                const CUtensorMap* tm = seg == 0 ? &maps.wq : seg < 3 ? &maps.wo : seg == 3 ? (rank ? &maps.wu : &maps.wg) : &maps.wd;
                const bool half = seg == 2 || seg == 5;
                const int no = half ? 1 : seg == 3 ? 9 : 4;
                const int ni = seg == 1 ? 8 : seg == 2 ? 4 : seg == 5 ? 5 : 9;
                const int dcol = seg == 0 ? -128 : seg == 3 ? 64 : 128;
                int col = seg == 0 ? (hg * 4 + 3) * 128 + rank * 64 : seg == 3 ? hg * 576 : half ? 512 : rank * 64;
                const int row0 = (seg == 0 || seg == 3 ? 0 : seg < 3 ? hg * 512 : hg * 576) + (half ? rank * 64 : 0);
                const int drow = half ? 128 : 64;
                uint32_t ns = 8;
                if (seg == 4) bits ^= 0xc0u;
#pragma unroll 1
                for (int o = 0; o < no; o++, col += dcol) {
                    if (seg == 3) {
                        ns = gu_slots(o);
                        if (slot >= ns) slot = 0;
                    }
#pragma unroll 1
                    for (int i = 0; i < ni; i++) {
                        const uint32_t es = slot | (seg == 1 && o == 0);
                        mbar_wait(empty0 + es * 8, (bits >> es) & 1);
                        warp_expect_tx(full0 + slot * 8, SLOT_BYTES);
                        warp_tma_mc(dst0 + slot * SLOT_BYTES, tm, full0 + slot * 8, col, row0 + i * drow);
                        bits ^= 1u << slot;
                        if (++slot == ns) slot = 0;
                    }
                    if (seg == 3 && o >= 2) {
                        const int i = (o - 2) * 16 + qt;
                        if (i < 81) warp_prefetch_l2(&maps.wd, (i % 9) * 64, hg * 576 + (i / 9) * 64);
                    }
                }
                if (seg == 0) {
                    const int kv0 = hg * 4 * SEQ;
#pragma unroll 1
                    for (int u = 0; u < 128; u++) {
                        const bool isv = u == 127 || (u > 0 && !(u & 1));
                        const int t = u == 127 ? 63 : isv ? (u >> 1) - 1 : (u + 1) >> 1;
                        const uint32_t es = slot + 1;
                        mbar_wait(empty0 + es * 8, (bits >> es) & 1);
                        warp_expect_tx(full0 + es * 8, 2 * SLOT_BYTES);
                        const CUtensorMap* km = isv ? &maps.v : &maps.k;
                        const int row = kv0 + t * 128 + (isv ? 0 : rank * 64), c0 = isv ? rank * 64 : 0;
                        warp_tma_mc(dst0 + slot * SLOT_BYTES, km, full0 + es * 8, c0, row);
                        warp_tma_mc(dst0 + es * SLOT_BYTES, km, full0 + es * 8, isv ? c0 : 64, isv ? row + 64 : row);
                        bits ^= 1u << es;
                        slot = (slot + 2) & 7;
                        if (isv) {
                            if (t < 60 && qt < 8)
                                warp_prefetch_l2((qt & 4) ? &maps.v : &maps.k, (qt & 1) * 64, kv0 + (t + 4) * 128 + (qt & 2) * 32);
                            if (t >= 44) {
                                const int i = (t - 44) * 16 + qt;
                                if (i < 72) warp_prefetch_l2(&maps.wo, (i % 9) * 64, hg * 512 + (i / 9) * 64);
                                else if (i < 234) {
                                    const int j = i < 153 ? i - 72 : i - 153;
                                    warp_prefetch_l2(i < 153 ? &maps.wg : &maps.wu, hg * 576 + (j / 9) * 64, (j % 9) * 64);
                                }
                            }
                        }
                    }
                }
            }
        } else {
            const int ht = tid - 288, lane = tid & 31;
            const uint32_t epoch = __ldcg(&g_cnt[C_B4 + (qt * 8 + hg) * 8]) / 8 + 1;
            {
                const uint32_t tag = (epoch & 0xffffu) << 16;
                while ((uint32_t)clock64() - t_entry < 2500u) {}
                uint4 v[3];
                uint32_t n = 0, bad;
#pragma unroll 1
                do {
                    if (++n > SPIN_LIMIT) die();
                    bad = 0;
#pragma unroll
                    for (int i = 0; i < 3; i++)
                        asm volatile("ld.relaxed.gpu.global.v4.u32 {%0,%1,%2,%3}, [%4];" : "=r"(v[i].x), "=r"(v[i].y), "=r"(v[i].z), "=r"(v[i].w)
                                     : "l"(g_tab1 + (ht + 96 * i) * 4) : "memory");
#pragma unroll
                    for (int i = 0; i < 3; i++) bad |= (v[i].x ^ tag) | (v[i].y ^ tag) | (v[i].z ^ tag) | (v[i].w ^ tag);
                } while (__any_sync(0xffffffffu, (bad >> 16) != 0));
#pragma unroll
                for (int i = 0; i < 3; i++)
                    *reinterpret_cast<uint2*>(smem + TAB_OFF + (ht & 3) * TAB_STRIDE + ((ht >> 2) + 24 * i) * 8) =
                        make_uint2(__byte_perm(v[i].x, v[i].y, 0x5410), __byte_perm(v[i].z, v[i].w, 0x5410));
                __syncwarp();
                if (lane == 0) mbar_arrive_cluster(sb + XBAR_OFF + 24);
            }
            bar_sync<15, 352>();
            if (ht < 32) {
#pragma unroll 1
                for (int i = lane; i < 128; i += 32) {
                    const uint32_t v = i < 64 ? 0u : EMPTY;
                    *reinterpret_cast<uint4*>(smem + TAB_OFF + i * 16) = make_uint4(v, v, v, v);
                }
                asm volatile("fence.proxy.async.shared::cta;" ::: "memory");
                __syncwarp();
            }
            const int task = b + NCTA * (ht >> 5);
            const uint4* wp = reinterpret_cast<const uint4*>(w_mod + (size_t)lane * (6 * DM)) + 2 * DM / 8 + task;
            if (task < NMOD2) {
#pragma unroll 1
                for (int i = 0; i < 18; i++) asm volatile("prefetch.global.L2 [%0];" ::"l"(wp + i * (32 * 6 * DM / 8)));
            }
            __nanosleep(1500);
            if (task < NMOD2) {
                float acc[8];
#pragma unroll
                for (int e = 0; e < 8; e++) acc[e] = 0.f;
#pragma unroll 1
                for (int i = 0; i < 18; i++) fma8(acc, silu_bf16(cvec[lane + 32 * i]), __ldg(wp + i * (32 * 6 * DM / 8)));
                float v = round_bf16(warp_reduce8<true>(acc, lane));
                const int vec = task / 72, col = (task % 72) * 8 + (lane >> 2);
                if (vec == 2) v += 1.f;
                if (vec == 3) v *= 0.5f;
                const int k = vec == 1 ? 2 : vec == 2 ? 1 : vec;
                if ((lane & 3) == 0) g_tab2[(col >> 1) * 8 + k * 2 + (col & 1)] = __bfloat16_as_ushort(__float2bfloat16_rn(v));
                warp_signal_count(&g_cnt[C_MOD2]);
            }
            bar_sync<4, 352>();
#pragma unroll 1
            for (int k = 0; k < 2; k++) {
                if (ht < 64) {
                    if (k) __nanosleep(6000);
                    if (ht < 32) {
                        const int grp = qt * 8 + hg;
                        const uint4* dst = lane < 16 ? g_acc + (k * 128 + grp) * ACC_N + lane * 64 : g_part + (k * 128 + grp) * PART_N + (lane - 16) * 64;
                        asm volatile("cp.async.bulk.global.shared::cta.bulk_group [%0], [%1], 1024;" ::"l"(dst),
                                     "r"(sb + TAB_OFF + (lane < 16 ? 0 : 1024)) : "memory");
                        if (k == 0 && lane < 18)
                            asm volatile("cp.async.bulk.global.shared::cta.bulk_group [%0], [%1], 1024;" ::"l"(g_h2 + grp * H2_N + lane * 64),
                                         "r"(sb + TAB_OFF + 1024) : "memory");
                        asm volatile("cp.async.bulk.commit_group;\ncp.async.bulk.wait_group 0;" ::: "memory");
                        warp_signal_count(&g_cnt[C_ZERO + grp * 8]);
                    }
                    bar_sync_r(12 + (ht >> 5), 160);
                    __threadfence();
                    if (lane < 4) atomicAdd(&g_cnt[(k ? C_B4 : C_B2) + (qt * 8 + (ht >> 5) * 4 + lane) * 8], 1u);
                } else {
                    __nanosleep(k ? 20000 : 5000);
                    uint32_t n = 0;
                    while (!__all_sync(0xffffffffu, (int)(ld_acquire(&g_cnt[C_ZERO + (qt * 8 + (lane & 7)) * 8]) - (2 * epoch - 1 + k)) >= 0)) {
                        __nanosleep(1000);
                        if (++n > SPIN_LIMIT) die();
                    }
                    if (lane == 0) mbar_arrive_cluster(sb + XBAR_OFF + 48);
                    bar_sync<14, 288>();
                    warp_wait_count(&g_cnt[C_MOD2], NMOD2 * epoch);
                    const uint4* res = reinterpret_cast<const uint4*>(k ? out : x) + (qt * 128 + hg * 16) * (DM / 8);
#pragma unroll 1
                    for (int i = lane; i < 1440; i += 32)
                        asm volatile("cp.async.cg.shared.global [%0], [%1], 16;" ::"r"(sb + S_OFF + i * 16),
                                     "l"(i < 1152 ? res + i : reinterpret_cast<const uint4*>(g_tab2) + (i - 1152))
                                     : "memory");
                    asm volatile("cp.async.wait_all;" ::: "memory");
                    __syncwarp();
                    if (lane == 0) mbar_arrive_cluster(sb + XBAR_OFF + 40);
                }
            }
        }
        __syncwarp();
        cluster_arrive();
        cluster_wait();
    } else {
        TSTAMP(0);
        cluster_arrive();
        const int lane = tid & 31;
        const int warp = __shfl_sync(0xffffffffu, tid >> 5, 0);
        const int g = lane >> 2, c = lane & 3;
        const int t128 = tid & 127;
        const uint32_t epoch_raw = __ldcg(&g_cnt[C_B4 + (qt * 8 + hg) * 8]);
        __nv_bfloat16 cv[5];
#pragma unroll
        for (int i = 0; i < 5; i++) cv[i] = cvec[min((tid >> 1) + 128 * i, DM - 1)];
        cluster_wait();
        if (b < NMOD1) {
            float sv[5];
#pragma unroll
            for (int i = 0; i < 5; i++) sv[i] = silu_bf16(cv[i]);
            float acc[8];
#pragma unroll
            for (int e = 0; e < 8; e++) acc[e] = 0.f;
            mbar_wait(sb + XBAR_OFF + 32, 0);
            TSTAMP(15);
#pragma unroll
            for (int i = 0; i < 5; i++)
                if (i < 4 || tid < 128) fma8(acc, sv[i], *reinterpret_cast<const uint4*>(smem + WM_OFF + tid * 16 + i * 4096));
            const float r1 = warp_reduce8<false>(acc, lane);
            float* part = reinterpret_cast<float*>(smem + PART_OFF);
            if ((lane & 2) == 0) part[warp * 16 + (lane & 1) * 8 + g] = r1;
            if (warp == 7) {
                bar_sync<1, 256>();
                if (lane < 16) {
                    float v = 0.f;
#pragma unroll
                    for (int w = 0; w < 8; w++) v += part[w * 16 + lane];
                    v = round_bf16(v);
                    const int is_ca = b >= NMOD1 / 2;
                    const int col = (b - is_ca * (NMOD1 / 2)) * 16 + lane;
                    if (is_ca) v += 1.f;
                    const uint32_t word = __bfloat16_as_ushort(__float2bfloat16_rn(v)) | ((epoch_raw / 8 + 1) << 16);
                    asm volatile("st.relaxed.gpu.global.u32 [%0], %1;" ::"l"(g_tab1 + (col >> 1) * 4 + (is_ca ? 0 : 2) + (col & 1)), "r"(word) : "memory");
                }
            } else {
                bar_arrive<1, 256>();
            }
        }
        const uint32_t epoch = __shfl_sync(0xffffffffu, epoch_raw / 8 + 1, 0);
        asm volatile("setmaxnreg.inc.sync.aligned.u32 240;");
        TSTAMP(11);

        Ring rg;
        rg.slot = 0;
        rg.bits = 0;
        rg.ns = 8;
        rg.full0 = sb + BAR_OFF;
        rg.desc0 = (sb & 0x3FFFFu) >> 4;
        rg.signaller = (t128 == 0) || (t128 == 32);
        rg.rel0 = mapa(sb + BAR_OFF + 64, (t128 >> 5) & 1);

        uint32_t a[144];
        float acc[64];
        {
            const int row = (warp & 3) * 16 + (lane & 7) + ((lane >> 3) & 1) * 8;
            const uint32_t xb = sb + X_OFF + wg * 8192 + row * 128;
            float ds[2][4], d0[2][4], d1[2][4];
#pragma unroll
            for (int i = 0; i < 4; i++) ds[0][i] = ds[1][i] = d0[0][i] = d0[1][i] = d1[0][i] = d1[1][i] = 0.f;
#pragma unroll
            for (int kb = 0; kb < 9; kb++) {
                if (kb % 3 == 0) mbar_wait(sb + XBAR_OFF + (kb / 3) * 8, 0);
#pragma unroll
                for (int s = 0; s < 4; s++) {
                    const int i = (kb * 4 + s) * 4;
                    ldsm4(xb + kb * SLOT_BYTES + (((2 * s + (lane >> 4)) ^ (lane & 7)) << 4), a[i], a[i + 1], a[i + 2], a[i + 3]);
                }
#pragma unroll
                for (int s = 0; s < 4; s++) {
                    const int i = (kb * 4 + s) * 4;
                    mma_sync(ds[s & 1], a[i], a[i + 1], a[i + 2], a[i + 3], 0x3F803F80u, 0x3F803F80u);
                    mma_k8(d0[0], a[i], a[i + 1], a[i]);
                    mma_k8(d1[0], a[i], a[i + 1], a[i + 1]);
                    mma_k8(d0[1], a[i + 2], a[i + 3], a[i + 2]);
                    mma_k8(d1[1], a[i + 2], a[i + 3], a[i + 3]);
                }
            }
            TSTAMP(12);
            const int src = 4 * g + (g >> 1);
            const float q0 = __shfl_sync(0xffffffffu, (g & 1) ? d0[0][1] + d0[1][1] : d0[0][0] + d0[1][0], src);
            const float q1 = __shfl_sync(0xffffffffu, (g & 1) ? d1[0][3] + d1[1][3] : d1[0][2] + d1[1][2], src);
            const float mean0 = (ds[0][0] + ds[1][0]) * (1.f / DM), mean1 = (ds[0][2] + ds[1][2]) * (1.f / DM);
            const float var0 = fmaxf(q0 * (1.f / DM) - mean0 * mean0, 0.f);
            const float var1 = fmaxf(q1 * (1.f / DM) - mean1 * mean1, 0.f);
            const float r0 = rsqrtf(var0 + 1e-5f), r1 = rsqrtf(var1 + 1e-5f);
            const float rh0 = round_bf16(r0), rh1 = round_bf16(r1);
            const uint32_t RH[2] = {pack_bf16(rh0, rh0), pack_bf16(rh1, rh1)};
            const uint32_t RL[2] = {pack_bf16(r0 - rh0, r0 - rh0), pack_bf16(r1 - rh1, r1 - rh1)};
            const uint32_t OF[2] = {pack_bf16(-mean0 * r0, -mean0 * r0), pack_bf16(-mean1 * r1, -mean1 * r1)};
            bar_sync<6, 256>();
            for (int i = 3; i < 8; i++) rg.release(i);
            TSTAMP(13);
            mbar_wait(sb + XBAR_OFF + 24, 0);
            TSTAMP(1);
            const uint32_t tab = sb + TAB_OFF + c * TAB_STRIDE;
            gemm_tile128(acc, a, rg, wg, true, [&](int kb) {
#pragma unroll
                for (int s = 4 * kb; s < 4 * kb + 4; s++) {
                    uint32_t t[4];
                    lds128(tab + s * 16, t[0], t[1], t[2], t[3]);
#pragma unroll
                    for (int e = 0; e < 4; e++) {
                        const uint32_t v = a[4 * s + e];
                        a[4 * s + e] = hfma2_bf16(hfma2_bf16(v, RH[e & 1], hfma2_bf16(v, RL[e & 1], OF[e & 1])), t[e & 2], t[(e & 2) + 1]);
                        asm volatile("" : "+r"(a[4 * s + e])::"memory");
                    }
                }
            });
        }
        bar_arrive<15, 352>();

#pragma unroll 1
        for (int ph = 0;; ph++) {
            const int xg = (ph >> 1) * 128 + qt * 8;
#pragma unroll 1
            for (int t = 0;; t++) {
                if (ph == 2) rg.resize(gu_slots(t));
                if ((ph & 1) || t) gemm_tile128(acc, a, rg, wg, ph != 1, [](int) {});
                if (ph & 1) {
                    uint4* dst = g_acc + (xg + warp) * ACC_N + t * 256 + (tid_now() & 31);
#pragma unroll
                    for (int j = 0; j < 8; j++) red_bf16x8(dst + j * 32, acc + 8 * j);
                    if (t == 3) break;
                } else {
                    if (ph == 2) {
#pragma unroll
                        for (int i = 0; i < 32; i++) {
                            const float gv = acc[i];
                            const float z = gv * fmaf(gv * gv, 0.7978845608028654f * 0.044715f, 0.7978845608028654f);
                            const float gu = gv * acc[32 + i];
                            acc[i] = fmaf(gu, tanh_fast(z), gu);
                        }
                    }
                    if (t == (ph == 0 ? 3 : 8)) break;
                    const uint32_t dst = sb + (tid_now() & 127) * 16 + (ph == 0 ? S_OFF + (2 - t) * 32768 + wg * 16384 : hh_off(t) + wg * 8192);
#pragma unroll
                    for (int i = 0; i < 8; i++)
                        if (i < 4 || ph == 0)
                            sts128(dst + i * 2048, pack_bf16(acc[8 * i], acc[8 * i + 1]), pack_bf16(acc[8 * i + 2], acc[8 * i + 3]),
                                   pack_bf16(acc[8 * i + 4], acc[8 * i + 5]), pack_bf16(acc[8 * i + 6], acc[8 * i + 7]));
                }
            }
            TSTAMP(2 + ph * 2);
            if (ph == 0) {
                uint32_t q[32], p[32];
                float s[64], o[64];
                pack_frag(q, acc);
#pragma unroll
                for (int i = 0; i < 32; i++) p[i] = 0u;
#pragma unroll
                for (int i = 0; i < 64; i++) o[i] = 0.f;
                float n0, n1, l0 = 1.f, l1 = 1.f;
                const uint32_t stash_u = sb + S_OFF + wg * 16384;
                const int bar_mine = 2 + wg, bar_other = 3 - wg;
                if (wg == 1) bar_arrive_r(2, 256);
                uint32_t ks = rg.wait_pair();
#pragma unroll 1
                for (int h = 0; h < 4; h++) {
                    {
                        const uint32_t stash = stash_u + (h - 1) * 32768 + (tid_now() & 127) * 16;
                        if (h) {
#pragma unroll
                            for (int i = 0; i < 8; i++) lds128(stash + i * 2048, q[4 * i], q[4 * i + 1], q[4 * i + 2], q[4 * i + 3]);
                        }
                        bar_sync_r(bar_mine, 256);
                        wg_fence();
                        issue_qk(s, q, rg.desc_of(ks));
                        uint32_t vs = ks;
                        if (h) vs = rg.wait_pair();
                        wg_fence();
                        issue_pv(o, p, rg.desc_of(vs));
                        bar_arrive_r(bar_other, 256);
                        if (h == 3) bar_arrive<4, 352>();
                        float f0 = l0 + __shfl_xor_sync(0xffffffffu, l0, 1);
                        float f1 = l1 + __shfl_xor_sync(0xffffffffu, l1, 1);
                        f0 = rcp_fast(f0 + __shfl_xor_sync(0xffffffffu, f0, 2));
                        f1 = rcp_fast(f1 + __shfl_xor_sync(0xffffffffu, f1, 2));
                        wg_wait<1>();
                        fence_regs(s);
                        if (h) rg.release_pair(ks);
                        row_max(s, n0, n1);
                        n0 *= -SCALE_LOG2;
                        n1 *= -SCALE_LOG2;
                        const bool ok = rg.try_pair();
                        uint32_t pt[2 * JSPLIT0];
                        l0 = 0.f;
                        l1 = 0.f;
                        exp_pack<0, JSPLIT0>(pt, s, n0, n1, l0, l1);
                        fence_regs(pt);
                        asm volatile("" : "+f"(l0), "+f"(l1), "+f"(f0), "+f"(f1)::"memory");
                        ks = rg.finish_pair(ok);
                        wg_wait<0>();
                        fence_regs(o);
                        fence_regs(p);
                        rg.release_pair(vs);
#pragma unroll
                        for (int i = 0; i < 2 * JSPLIT0; i++) p[i] = pt[i];
                        exp_pack<JSPLIT0, 16>(p, s, n0, n1, l0, l1);
#pragma unroll
                        for (int i = 0; i < 8; i++)
                            sts128_if(h, stash + i * 2048, pack_bf16(o[8 * i] * f0, o[8 * i + 1] * f0), pack_bf16(o[8 * i + 2] * f1, o[8 * i + 3] * f1),
                                      pack_bf16(o[8 * i + 4] * f0, o[8 * i + 5] * f0), pack_bf16(o[8 * i + 6] * f1, o[8 * i + 7] * f1));
                    }
#pragma unroll 1
                    for (int j = 1; j < 16; j++) {
                        bar_sync_r(bar_mine, 256);
                        wg_fence();
                        issue_qk(s, q, rg.desc_of(ks));
                        const uint32_t vs = rg.wait_pair();
                        wg_fence();
                        issue_pv(o, p, rg.desc_of(vs), j > 1);
                        bar_arrive_r(bar_other, 256);
                        wg_wait<1>();
                        fence_regs(s);
                        rg.release_pair(ks);
                        const bool ok = rg.try_pair();
                        uint32_t pt[2 * JSPLIT];
                        float t0 = 0.f, t1 = 0.f;
                        exp_pack<0, JSPLIT>(pt, s, n0, n1, t0, t1);
                        fence_regs(pt);
                        asm volatile("" : "+f"(t0), "+f"(t1)::"memory");
                        ks = rg.finish_pair(ok);
                        wg_wait<0>();
                        fence_regs(o);
                        fence_regs(p);
                        rg.release_pair(vs);
#pragma unroll
                        for (int i = 0; i < 2 * JSPLIT; i++) p[i] = pt[i];
                        exp_pack<JSPLIT, 16>(p, s, n0, n1, t0, t1);
                        if (__builtin_expect(__any_sync(0xffffffffu, !(t0 + t1 < P_BOUND)), 0)) {
                            float x0, x1;
                            row_max(s, x0, x1);
                            x0 = fminf(x0 * -SCALE_LOG2, n0);
                            x1 = fminf(x1 * -SCALE_LOG2, n1);
                            const float al0 = ex2(x0 - n0), al1 = ex2(x1 - n1);
                            n0 = x0;
                            n1 = x1;
                            l0 *= al0;
                            l1 *= al1;
#pragma unroll
                            for (int i = 0; i < 16; i++) {
                                o[4 * i] *= al0;
                                o[4 * i + 1] *= al0;
                                o[4 * i + 2] *= al1;
                                o[4 * i + 3] *= al1;
                            }
                            t0 = 0.f;
                            t1 = 0.f;
                            exp_pack<0, 16>(p, s, n0, n1, t0, t1);
                        }
                        l0 += t0;
                        l1 += t1;
                    }
                }
                bar_sync_r(bar_mine, 256);
                wg_fence();
                issue_pv(o, p, rg.desc_of(ks));
                if (wg == 0) bar_arrive_r(3, 256);
                float f0 = l0 + __shfl_xor_sync(0xffffffffu, l0, 1);
                float f1 = l1 + __shfl_xor_sync(0xffffffffu, l1, 1);
                f0 = rcp_fast(f0 + __shfl_xor_sync(0xffffffffu, f0, 2));
                f1 = rcp_fast(f1 + __shfl_xor_sync(0xffffffffu, f1, 2));
                mbar_wait(sb + XBAR_OFF + 48, 0);
                wg_wait<0>();
                fence_regs(o);
                rg.release_pair(ks);
#pragma unroll
                for (int i = 0; i < 16; i++) {
                    a[96 + 2 * i] = pack_bf16(o[4 * i] * f0, o[4 * i + 1] * f0);
                    a[97 + 2 * i] = pack_bf16(o[4 * i + 2] * f1, o[4 * i + 3] * f1);
                }
                const uint32_t stash0 = stash_u + (tid_now() & 127) * 16;
#pragma unroll
                for (int i = 0; i < 24; i++)
                    lds128(stash0 + (i >> 3) * 32768 + (i & 7) * 2048, a[4 * i], a[4 * i + 1], a[4 * i + 2], a[4 * i + 3]);
#pragma unroll
                for (int i = 128; i < 144; i++) a[i] = 0u;
                bar_arrive<14, 288>();
                kill_regs(acc);
                TSTAMP(3);
            } else if (ph == 2) {
#pragma unroll
                for (int i = 0; i < 16; i++) a[128 + i] = pack_bf16(acc[2 * i], acc[2 * i + 1]);
                const uint32_t hh = sb + wg * 8192 + (tid_now() & 127) * 16;
#pragma unroll
                for (int i = 31; i >= 0; i--) lds128(hh + hh_off(i >> 2) + (i & 3) * 2048, a[4 * i], a[4 * i + 1], a[4 * i + 2], a[4 * i + 3]);
                bar_arrive<14, 288>();
                mbar_wait(sb + XBAR_OFF + 48, 1);
                bar_sync_r(8 + wg, 128);
                rg.release_nobranch(6);
                rg.release_nobranch(7);
                rg.ns = 8;
                kill_regs(acc);
            } else {
                const int lane = tid_now() & 31, g = lane >> 2, c = lane & 3;
                bar_arrive_r(12 + wg, 160);
                {
                    float acc2[32];
                    gemm_tile64(acc2, a, rg, ph != 1);
                    uint4* dst = g_part + (xg + warp) * PART_N + hg * 128 + lane;
#pragma unroll
                    for (int j = 0; j < 4; j++)
                        st_b128(dst + j * 32, pack_bf16(acc2[8 * j], acc2[8 * j + 1]), pack_bf16(acc2[8 * j + 2], acc2[8 * j + 3]),
                                pack_bf16(acc2[8 * j + 4], acc2[8 * j + 5]), pack_bf16(acc2[8 * j + 6], acc2[8 * j + 7]));
                }
                TSTAMP(3 + ph * 2);
                const bool last_ok = lane < 16;
                const int roff = (qt * 128 + hg * 16 + warp) * (DM / 2) + g * 8 + c;
                uint32_t rv[5][4];
                uint4 tb[5][2];
                warp_wait_count(g_cnt + (ph == 1 ? C_B2 : C_B4) + (qt * 8 + hg) * 8, 8 * epoch);
                TSTAMP(16 + ph);
                uint4 av[5];
#pragma unroll
                for (int i = 0; i < 4; i++) av[i] = __ldcg(g_acc + (xg + hg) * ACC_N + (g + 8 * i) * 32 + warp * 4 + c);
                mbar_wait(sb + XBAR_OFF + 40, ph >> 1);
                {
                    const uint32_t* res = reinterpret_cast<const uint32_t*>(smem + S_OFF) + warp * (DM / 2) + g * 8 + c;
                    const uint4* t2 = reinterpret_cast<const uint4*>(smem + S_OFF) + 1152 + g * 8 + c;
#pragma unroll
                    for (int i = 0; i < 5; i++) {
                        const int o = (i < 4 || last_ok) ? i * 64 : 0;
                        rv[i][0] = res[o];
                        rv[i][1] = res[o + 4 * DM];
                        rv[i][2] = res[o + 4];
                        rv[i][3] = res[o + 4 * DM + 4];
                        tb[i][0] = t2[o];
                        tb[i][1] = t2[o + 4];
                    }
                }
                {
                    const uint4* pp = g_part + (xg + hg) * PART_N + (g >> 2) * 512 + (g & 3) * 32 + warp * 4 + c;
                    uint4 pv[4];
                    uint32_t n = 0;
#pragma unroll 1
                    do {
                        if (++n > SPIN_LIMIT) die();
#pragma unroll
                        for (int k = 0; k < 4; k++) pv[k] = ld_b128(pp + k * 128);
                    } while (!__all_sync(0xffffffffu, pv[0].x != EMPTY && pv[1].x != EMPTY && pv[2].x != EMPTY && pv[3].x != EMPTY));
                    float f[8];
                    f[0] = (bf_lo(pv[0].x) + bf_lo(pv[1].x)) + (bf_lo(pv[2].x) + bf_lo(pv[3].x));
                    f[1] = (bf_hi(pv[0].x) + bf_hi(pv[1].x)) + (bf_hi(pv[2].x) + bf_hi(pv[3].x));
                    f[2] = (bf_lo(pv[0].y) + bf_lo(pv[1].y)) + (bf_lo(pv[2].y) + bf_lo(pv[3].y));
                    f[3] = (bf_hi(pv[0].y) + bf_hi(pv[1].y)) + (bf_hi(pv[2].y) + bf_hi(pv[3].y));
                    f[4] = (bf_lo(pv[0].z) + bf_lo(pv[1].z)) + (bf_lo(pv[2].z) + bf_lo(pv[3].z));
                    f[5] = (bf_hi(pv[0].z) + bf_hi(pv[1].z)) + (bf_hi(pv[2].z) + bf_hi(pv[3].z));
                    f[6] = (bf_lo(pv[0].w) + bf_lo(pv[1].w)) + (bf_lo(pv[2].w) + bf_lo(pv[3].w));
                    f[7] = (bf_hi(pv[0].w) + bf_hi(pv[1].w)) + (bf_hi(pv[2].w) + bf_hi(pv[3].w));
#pragma unroll
                    for (int e = 0; e < 8; e++) f[e] += __shfl_xor_sync(0xffffffffu, f[e], 16);
                    av[4] = make_uint4(pack_bf16(f[0], f[1]), pack_bf16(f[2], f[3]), pack_bf16(f[4], f[5]), pack_bf16(f[6], f[7]));
                }
                TSTAMP(17 + ph);
#pragma unroll
                for (int i = 0; i < 5; i++) {
                    const uint32_t g0 = ph == 1 ? tb[i][0].x : tb[i][0].w, g1 = ph == 1 ? tb[i][1].x : tb[i][1].w;
                    rv[i][0] = hfma2_bf16(av[i].x, g0, rv[i][0]);
                    rv[i][1] = hfma2_bf16(av[i].y, g0, rv[i][1]);
                    rv[i][2] = hfma2_bf16(av[i].z, g1, rv[i][2]);
                    rv[i][3] = hfma2_bf16(av[i].w, g1, rv[i][3]);
                }
                if (ph == 1) {
                    float sm[2] = {0.f, 0.f}, sq[2] = {0.f, 0.f};
#pragma unroll
                    for (int i = 0; i < 5; i++) {
#pragma unroll
                        for (int e = 0; e < 4; e++) {
                            const uint32_t v = (i < 4 || last_ok) ? rv[i][e] : 0u;
                            const float lo = bf_lo(v), hi = bf_hi(v);
                            sm[e & 1] += lo + hi;
                            sq[e & 1] = fmaf(lo, lo, fmaf(hi, hi, sq[e & 1]));
                        }
                    }
#pragma unroll
                    for (int m = 1; m < 32; m <<= 1) {
                        sm[0] += __shfl_xor_sync(0xffffffffu, sm[0], m);
                        sm[1] += __shfl_xor_sync(0xffffffffu, sm[1], m);
                        sq[0] += __shfl_xor_sync(0xffffffffu, sq[0], m);
                        sq[1] += __shfl_xor_sync(0xffffffffu, sq[1], m);
                    }
                    float rs[2], of[2];
#pragma unroll
                    for (int e = 0; e < 2; e++) {
                        const float mean = sm[e] * (1.f / DM);
                        rs[e] = rsqrtf(fmaxf(sq[e] * (1.f / DM) - mean * mean, 0.f) + 1e-5f);
                        of[e] = -mean * rs[e];
                    }
                    uint4* own = g_h2 + (qt * 8 + hg) * H2_N + g * 32 + warp * 4 + c;
#pragma unroll
                    for (int i = 0; i < 5; i++) {
                        uint32_t h[4];
#pragma unroll
                        for (int e = 0; e < 4; e++) {
                            const uint32_t n = pack_bf16(fmaf(bf_lo(rv[i][e]), rs[e & 1], of[e & 1]), fmaf(bf_hi(rv[i][e]), rs[e & 1], of[e & 1]));
                            h[e] = hfma2_bf16(n, tb[i][e >> 1].y, tb[i][e >> 1].z);
                        }
                        if (i < 4 || last_ok) st_b128(own + i * 256, h[0], h[1], h[2], h[3]);
                    }
                    TSTAMP(21);
                }
                {
                    uint32_t* o0 = reinterpret_cast<uint32_t*>(out) + roff;
#pragma unroll
                    for (int i = 0; i < 5; i++) {
                        if (i < 4 || last_ok) {
                            o0[i * 64] = rv[i][0];
                            o0[i * 64 + 4 * DM] = rv[i][1];
                            o0[i * 64 + 4] = rv[i][2];
                            o0[i * 64 + 4 * DM + 4] = rv[i][3];
                        }
                    }
                }
                if (ph == 3) break;
                const uint4* h2 = g_h2 + (qt * 8 + warp) * H2_N + lane;
                {
                    uint32_t n = 0;
                    while (!__all_sync(0xffffffffu, ld_b128(h2 + 35 * 32).x != EMPTY)) {
                        if (++n > SPIN_LIMIT) die();
                    }
                    TSTAMP(23);
                    auto load_kb = [&](int kb) {
#pragma unroll
                        for (int i = 4 * kb; i < 4 * kb + 4; i++) {
                            const uint4 t = ld_b128(h2 + i * 32);
                            a[4 * i] = t.x;
                            a[4 * i + 1] = t.y;
                            a[4 * i + 2] = t.z;
                            a[4 * i + 3] = t.w;
                        }
                    };
                    load_kb(0);
                    load_kb(1);
                    load_kb(2);
                    gemm_tile128(acc, a, rg, wg, true, [&](int kb) {
#pragma unroll 1
                        while (__any_sync(0xffffffffu, max(max(a[16 * kb], a[16 * kb + 4]), max(a[16 * kb + 8], a[16 * kb + 12])) == EMPTY)) {
                            if (++n > SPIN_LIMIT) die();
                            load_kb(kb);
                        }
                        if (kb + 3 < 9) load_kb(kb + 3);
                    });
                }
            }
        }
        TSTAMP(10);
        __syncwarp();
        cluster_arrive();
        cluster_wait();
    }
}

typedef CUresult (*EncodeFn)(CUtensorMap*, CUtensorMapDataType, cuuint32_t, void*, const cuuint64_t*, const cuuint64_t*,
                             const cuuint32_t*, const cuuint32_t*, CUtensorMapInterleave, CUtensorMapSwizzle,
                             CUtensorMapL2promotion, CUtensorMapFloatOOBfill);

void make_map(EncodeFn enc, CUtensorMap* m, const void* ptr, uint64_t rows, uint64_t cols, bool slim = false) {
    cuuint64_t gd[2] = {cols, rows};
    cuuint64_t gs[1] = {cols * 2};
    cuuint32_t bx[2] = {slim ? 16u : 64u, slim ? 192u : 64u};
    cuuint32_t es[2] = {1, 1};
    enc(m, CU_TENSOR_MAP_DATA_TYPE_BFLOAT16, 2, const_cast<void*>(ptr), gd, gs, bx, es, CU_TENSOR_MAP_INTERLEAVE_NONE,
        slim ? CU_TENSOR_MAP_SWIZZLE_NONE : CU_TENSOR_MAP_SWIZZLE_128B,
        slim ? CU_TENSOR_MAP_L2_PROMOTION_NONE : CU_TENSOR_MAP_L2_PROMOTION_L2_128B, CU_TENSOR_MAP_FLOAT_OOB_FILL_NONE);
}

}

extern "C" void kernel_launch(void* const* d_in, const int* in_sizes, int n_in, void* d_out, int out_size) {
    (void)in_sizes; (void)n_in; (void)out_size;
    static EncodeFn enc = nullptr;
    if (!enc) {
        void* fn = nullptr;
        cudaDriverEntryPointQueryResult qr;
        cudaGetDriverEntryPoint("cuTensorMapEncodeTiled", &fn, cudaEnableDefault, &qr);
        enc = (EncodeFn)fn;
        cudaFuncSetAttribute(mega_kernel, cudaFuncAttributeMaxDynamicSharedMemorySize, SMEM_BYTES);
    }
    Maps maps;
    make_map(enc, &maps.x, d_in[0], SEQ, DM);
    make_map(enc, &maps.k, d_in[1], 32 * SEQ, DH);
    make_map(enc, &maps.v, d_in[2], 32 * SEQ, DH);
    make_map(enc, &maps.wq, d_in[3], DM, 4096);
    make_map(enc, &maps.wo, d_in[4], 4096, DM);
    make_map(enc, &maps.wg, d_in[6], DM, DF);
    make_map(enc, &maps.wu, d_in[7], DM, DF);
    make_map(enc, &maps.wd, d_in[8], DF, DM);
    make_map(enc, &maps.wm, d_in[10], DM, 6 * DM, true);
    mega_kernel<<<NCTA, 384, SMEM_BYTES>>>(maps, (const __nv_bfloat16*)d_in[0], (const __nv_bfloat16*)d_in[9],
                                           (const __nv_bfloat16*)d_in[10], (__nv_bfloat16*)d_out);
}
```
